```python
import torch

def _softmax(x, axis=-1):
    return torch.softmax(x, dim=axis)

def _gelu(x):
    return torch.nn.functional.gelu(x, approximate='tanh')

def _silu(x):
    return torch.nn.functional.silu(x)

def _sigmoid(x):
    return torch.sigmoid(x)

def _layernorm(x, axis=-1, eps=1e-05):
    m = x.mean(dim=axis, keepdim=True)
    v = x.var(dim=axis, keepdim=True, unbiased=False)
    return (x - m) / torch.sqrt(v + eps)

def _scatter_add(tgt, idx, src, axis=0):
    return tgt.clone().index_add_(axis, idx, src)

def _segment_sum(src, seg, n):
    out = torch.zeros((n,) + src.shape[1:], dtype=src.dtype)
    return out.index_add_(0, seg, src)

def _pad(x, pw):
    flat = tuple((v for pair in reversed(pw) for v in pair))
    return torch.nn.functional.pad(x, flat)
kernel_name = 'adaLN_cond__linear_kernel_hedgehog__dense_activation_squared_relu__prompt'

def setup_inputs():

    _w = lambda a: (lambda t: t.to(torch.bfloat16) if t.is_floating_point() else t)(torch.as_tensor(a))

    def _A_setup():
        B, S, D, H = (1, 2048, 1024, 32)
        Dh = D // H
        return {'x': _w((lambda *s: torch.randn(*s, dtype=torch.bfloat16) * 0.05)(B, S, D)), 'wqkv': _w((lambda *s: torch.randn(*s, dtype=torch.bfloat16) * 0.4)(D, 3 * D)), 'w_phi': _w((lambda *s: torch.randn(*s, dtype=torch.bfloat16) * 0.4)(H, Dh, Dh) * Dh ** (-0.5)), 'wo': _w((lambda *s: torch.randn(*s, dtype=torch.bfloat16) * 0.05)(D, D))}
    _A_in = _A_setup()

    def _B_setup():
        B, S, D, F = (1, 2048, 1024, 3584)
        return {'x': _w((lambda *s: torch.randn(*s, dtype=torch.bfloat16) * 0.05)(B, S, D)), 'w1': _w((lambda *s: torch.randn(*s, dtype=torch.bfloat16) * 0.05)(D, F)), 'b1': _w((lambda *s: torch.randn(*s, dtype=torch.bfloat16) * 0.4)(F)), 'w2': _w((lambda *s: torch.randn(*s, dtype=torch.bfloat16) * 0.05)(F, D)), 'b2': _w((lambda *s: torch.randn(*s, dtype=torch.bfloat16) * 6.4)(D))}
    _B_in = _B_setup()
    return {'A_x': _A_in['x'], 'A_wqkv': _A_in['wqkv'], 'A_w_phi': _A_in['w_phi'], 'A_wo': _A_in['wo'], 'B_x': _B_in['x'], 'B_w1': _B_in['w1'], 'B_b1': _B_in['b1'], 'B_w2': _B_in['w2'], 'B_b2': _B_in['b2'], 'c': _w((lambda *s: torch.randn(*s, dtype=torch.bfloat16) * 0.1)(1, 1024) * 8.0), 'w_mod': _w((lambda *s: torch.randn(*s, dtype=torch.bfloat16) * 0.1)(1024, 6 * 1024) * 1024 ** (-0.5) * 8.0)}

def reference(A_x, A_wqkv, A_w_phi, A_wo, B_x, B_w1, B_b1, B_w2, B_b2, c, w_mod):

    def _A_ref(x, wqkv, w_phi, wo):
        B, S, D = x.shape
        H = 32
        Dh = D // H
        qkv = (lambda x, *d: x.permute(*d))((x @ wqkv).reshape(B, S, 3, H, Dh), 2, 0, 3, 1, 4)
        q, k, v = (qkv[0], qkv[1], qkv[2])
        pq = torch.einsum('bhsd,hdf->bhsf', q, w_phi)
        pk = torch.einsum('bhsd,hdf->bhsf', k, w_phi)
        phi_q = torch.concatenate([_softmax(pq, axis=-1), _softmax(-pq, axis=-1)], axis=-1)
        phi_k = torch.concatenate([_softmax(pk, axis=-1), _softmax(-pk, axis=-1)], axis=-1)
        kv = torch.einsum('bhsf,bhsd->bhfd', phi_k, v)
        z = torch.einsum('bhsf->bhf', phi_k)
        num = torch.einsum('bhqf,bhfd->bhqd', phi_q, kv)
        den = torch.einsum('bhqf,bhf->bhq', phi_q, z)[..., None] + 1e-06
        o = num / den
        return (lambda x, *d: x.permute(*d))(o, 0, 2, 1, 3).reshape(B, S, D) @ wo

    def _B_ref(x, w1, b1, w2, b2):
        h = torch.einsum('bsd,df->bsf', x, w1) + b1
        zero = torch.zeros_like(h)
        r = torch.where(h > zero, h, zero)
        h = r * r
        out = torch.einsum('bsf,fd->bsd', h, w2) + b2
        return out
    x = A_x
    mod = (_silu(c) @ w_mod).reshape(c.shape[0], 6, 1, -1)
    sa, ca, ga, sb, cb, gb = (mod[:, 0].clone(), mod[:, 1].clone(), mod[:, 2].clone(), mod[:, 3].clone(), mod[:, 4].clone(), mod[:, 5].clone())
    h = _layernorm(x, axis=-1) * (1 + ca) + sa
    x = x + ga * _A_ref(h, A_wqkv, A_w_phi, A_wo)
    h = _layernorm(x, axis=-1) * (1 + cb) + sb
    x = x + gb * _B_ref(h, B_w1, B_b1, B_w2, B_b2)
    return x
```

```cpp
#include <cuda_runtime.h>
#include <cuda_bf16.h>
#include <cuda_fp16.h>
#include <cuda.h>
#include <stdint.h>

typedef __nv_bfloat16 bf16;
#define PACE 300

__device__ __forceinline__ void wgmma_ss_n128(float (&d)[64], uint64_t da, uint64_t db, int sd) {
  asm volatile("{\n.reg .pred p;\nsetp.ne.b32 p, %66, 0;\n"
    "wgmma.mma_async.sync.aligned.m64n128k16.f32.bf16.bf16 {%0, %1, %2, %3, %4, %5, %6, %7, %8, %9, %10, %11, %12, %13, %14, %15, %16, %17, %18, %19, %20, %21, %22, %23, %24, %25, %26, %27, %28, %29, %30, %31, %32, %33, %34, %35, %36, %37, %38, %39, %40, %41, %42, %43, %44, %45, %46, %47, %48, %49, %50, %51, %52, %53, %54, %55, %56, %57, %58, %59, %60, %61, %62, %63}, %64, %65, p, 1, 1, 0, 1;\n}\n"
    : "+f"(d[0]), "+f"(d[1]), "+f"(d[2]), "+f"(d[3]), "+f"(d[4]), "+f"(d[5]), "+f"(d[6]), "+f"(d[7]), "+f"(d[8]), "+f"(d[9]), "+f"(d[10]), "+f"(d[11]), "+f"(d[12]), "+f"(d[13]), "+f"(d[14]), "+f"(d[15]), "+f"(d[16]), "+f"(d[17]), "+f"(d[18]), "+f"(d[19]), "+f"(d[20]), "+f"(d[21]), "+f"(d[22]), "+f"(d[23]), "+f"(d[24]), "+f"(d[25]), "+f"(d[26]), "+f"(d[27]), "+f"(d[28]), "+f"(d[29]), "+f"(d[30]), "+f"(d[31]), "+f"(d[32]), "+f"(d[33]), "+f"(d[34]), "+f"(d[35]), "+f"(d[36]), "+f"(d[37]), "+f"(d[38]), "+f"(d[39]), "+f"(d[40]), "+f"(d[41]), "+f"(d[42]), "+f"(d[43]), "+f"(d[44]), "+f"(d[45]), "+f"(d[46]), "+f"(d[47]), "+f"(d[48]), "+f"(d[49]), "+f"(d[50]), "+f"(d[51]), "+f"(d[52]), "+f"(d[53]), "+f"(d[54]), "+f"(d[55]), "+f"(d[56]), "+f"(d[57]), "+f"(d[58]), "+f"(d[59]), "+f"(d[60]), "+f"(d[61]), "+f"(d[62]), "+f"(d[63])
    : "l"(da), "l"(db), "r"(sd));
}
__device__ __forceinline__ void wgmma_ss_n192(float (&d)[96], uint64_t da, uint64_t db, int sd) {
  asm volatile("{\n.reg .pred p;\nsetp.ne.b32 p, %98, 0;\n"
    "wgmma.mma_async.sync.aligned.m64n192k16.f32.bf16.bf16 {%0, %1, %2, %3, %4, %5, %6, %7, %8, %9, %10, %11, %12, %13, %14, %15, %16, %17, %18, %19, %20, %21, %22, %23, %24, %25, %26, %27, %28, %29, %30, %31, %32, %33, %34, %35, %36, %37, %38, %39, %40, %41, %42, %43, %44, %45, %46, %47, %48, %49, %50, %51, %52, %53, %54, %55, %56, %57, %58, %59, %60, %61, %62, %63, %64, %65, %66, %67, %68, %69, %70, %71, %72, %73, %74, %75, %76, %77, %78, %79, %80, %81, %82, %83, %84, %85, %86, %87, %88, %89, %90, %91, %92, %93, %94, %95}, %96, %97, p, 1, 1, 0, 1;\n}\n"
    : "+f"(d[0]), "+f"(d[1]), "+f"(d[2]), "+f"(d[3]), "+f"(d[4]), "+f"(d[5]), "+f"(d[6]), "+f"(d[7]), "+f"(d[8]), "+f"(d[9]), "+f"(d[10]), "+f"(d[11]), "+f"(d[12]), "+f"(d[13]), "+f"(d[14]), "+f"(d[15]), "+f"(d[16]), "+f"(d[17]), "+f"(d[18]), "+f"(d[19]), "+f"(d[20]), "+f"(d[21]), "+f"(d[22]), "+f"(d[23]), "+f"(d[24]), "+f"(d[25]), "+f"(d[26]), "+f"(d[27]), "+f"(d[28]), "+f"(d[29]), "+f"(d[30]), "+f"(d[31]), "+f"(d[32]), "+f"(d[33]), "+f"(d[34]), "+f"(d[35]), "+f"(d[36]), "+f"(d[37]), "+f"(d[38]), "+f"(d[39]), "+f"(d[40]), "+f"(d[41]), "+f"(d[42]), "+f"(d[43]), "+f"(d[44]), "+f"(d[45]), "+f"(d[46]), "+f"(d[47]), "+f"(d[48]), "+f"(d[49]), "+f"(d[50]), "+f"(d[51]), "+f"(d[52]), "+f"(d[53]), "+f"(d[54]), "+f"(d[55]), "+f"(d[56]), "+f"(d[57]), "+f"(d[58]), "+f"(d[59]), "+f"(d[60]), "+f"(d[61]), "+f"(d[62]), "+f"(d[63]), "+f"(d[64]), "+f"(d[65]), "+f"(d[66]), "+f"(d[67]), "+f"(d[68]), "+f"(d[69]), "+f"(d[70]), "+f"(d[71]), "+f"(d[72]), "+f"(d[73]), "+f"(d[74]), "+f"(d[75]), "+f"(d[76]), "+f"(d[77]), "+f"(d[78]), "+f"(d[79]), "+f"(d[80]), "+f"(d[81]), "+f"(d[82]), "+f"(d[83]), "+f"(d[84]), "+f"(d[85]), "+f"(d[86]), "+f"(d[87]), "+f"(d[88]), "+f"(d[89]), "+f"(d[90]), "+f"(d[91]), "+f"(d[92]), "+f"(d[93]), "+f"(d[94]), "+f"(d[95])
    : "l"(da), "l"(db), "r"(sd));
}
__device__ __forceinline__ void wgmma_rs_n8(float (&d)[4], uint32_t a0, uint32_t a1, uint32_t a2, uint32_t a3, uint64_t db, int sd) {
  asm volatile("{\n.reg .pred p;\nsetp.ne.b32 p, %9, 0;\n"
    "wgmma.mma_async.sync.aligned.m64n8k16.f32.bf16.bf16 {%0, %1, %2, %3}, {%4, %5, %6, %7}, %8, p, 1, 1, 1;\n}\n"
    : "+f"(d[0]), "+f"(d[1]), "+f"(d[2]), "+f"(d[3])
    : "r"(a0), "r"(a1), "r"(a2), "r"(a3), "l"(db), "r"(sd));
}
__device__ __forceinline__ void wgmma_rs_n32(float (&d)[16], uint32_t a0, uint32_t a1, uint32_t a2, uint32_t a3, uint64_t db, int sd) {
  asm volatile("{\n.reg .pred p;\nsetp.ne.b32 p, %21, 0;\n"
    "wgmma.mma_async.sync.aligned.m64n32k16.f32.bf16.bf16 {%0, %1, %2, %3, %4, %5, %6, %7, %8, %9, %10, %11, %12, %13, %14, %15}, {%16, %17, %18, %19}, %20, p, 1, 1, 1;\n}\n"
    : "+f"(d[0]), "+f"(d[1]), "+f"(d[2]), "+f"(d[3]), "+f"(d[4]), "+f"(d[5]), "+f"(d[6]), "+f"(d[7]), "+f"(d[8]), "+f"(d[9]), "+f"(d[10]), "+f"(d[11]), "+f"(d[12]), "+f"(d[13]), "+f"(d[14]), "+f"(d[15])
    : "r"(a0), "r"(a1), "r"(a2), "r"(a3), "l"(db), "r"(sd));
}
__device__ __forceinline__ void wgmma_rs_n40(float (&d)[20], uint32_t a0, uint32_t a1, uint32_t a2, uint32_t a3, uint64_t db, int sd) {
  asm volatile("{\n.reg .pred p;\nsetp.ne.b32 p, %25, 0;\n"
    "wgmma.mma_async.sync.aligned.m64n40k16.f32.bf16.bf16 {%0, %1, %2, %3, %4, %5, %6, %7, %8, %9, %10, %11, %12, %13, %14, %15, %16, %17, %18, %19}, {%20, %21, %22, %23}, %24, p, 1, 1, 1;\n}\n"
    : "+f"(d[0]), "+f"(d[1]), "+f"(d[2]), "+f"(d[3]), "+f"(d[4]), "+f"(d[5]), "+f"(d[6]), "+f"(d[7]), "+f"(d[8]), "+f"(d[9]), "+f"(d[10]), "+f"(d[11]), "+f"(d[12]), "+f"(d[13]), "+f"(d[14]), "+f"(d[15]), "+f"(d[16]), "+f"(d[17]), "+f"(d[18]), "+f"(d[19])
    : "r"(a0), "r"(a1), "r"(a2), "r"(a3), "l"(db), "r"(sd));
}
__device__ __forceinline__ void wgmma_ss_n40_tt(float (&d)[20], uint64_t da, uint64_t db, int sd) {
  asm volatile("{\n.reg .pred p;\nsetp.ne.b32 p, %22, 0;\n"
    "wgmma.mma_async.sync.aligned.m64n40k16.f32.bf16.bf16 {%0, %1, %2, %3, %4, %5, %6, %7, %8, %9, %10, %11, %12, %13, %14, %15, %16, %17, %18, %19}, %20, %21, p, 1, 1, 1, 1;\n}\n"
    : "+f"(d[0]), "+f"(d[1]), "+f"(d[2]), "+f"(d[3]), "+f"(d[4]), "+f"(d[5]), "+f"(d[6]), "+f"(d[7]), "+f"(d[8]), "+f"(d[9]), "+f"(d[10]), "+f"(d[11]), "+f"(d[12]), "+f"(d[13]), "+f"(d[14]), "+f"(d[15]), "+f"(d[16]), "+f"(d[17]), "+f"(d[18]), "+f"(d[19])
    : "l"(da), "l"(db), "r"(sd));
}

namespace {

constexpr int SEQ = 2048, DM = 1024, FF = 3584;
constexpr int RING = 163840;
constexpr int OFF_E0 = RING;
constexpr int OFF_E1 = OFF_E0 + 32768;
constexpr int OFF_WPHI = OFF_E1 + 20480;
constexpr int OFF_VEC = OFF_WPHI + 8192;
constexpr int OFF_RED = OFF_VEC + 2944;
constexpr int OFF_BAR = OFF_RED + 3072;
constexpr int SMEM_BYTES = OFF_BAR + 400;
static_assert(SMEM_BYTES <= 232448, "smem");
constexpr int B_FULL = 0, B_EMPTY = 5, B_FULL2 = 10, B_INIT = 14, B_STG = 19, B_EFREE = 29, B_ISS = 39, B_KVOK = 44, B_RLY = 46, B_XBAR = 47;
constexpr int S_KV = 1, S_O = 3, S_H2 = 4, S_F1 = 5, S_O0 = 9;

struct Params {
  CUtensorMap a_h, a_o, a_h1;
  CUtensorMap b_kv, b_q, b_wo, b_w1x, b_w1, b_w2;
  CUtensorMap t_x, t_h, t_o, t_h1, t_out;
  const bf16* wphi; const bf16* b1; const bf16* b2; const bf16* c; const bf16* wmod;
};

}

__device__ __align__(1024) bf16 g_o[SEQ * DM];
__device__ __align__(1024) bf16 g_h[SEQ * DM];
__device__ __align__(1024) bf16 g_h1[SEQ * FF];
__device__ __align__(128) float g_kv[32 * 64 * 32];
__device__ __align__(128) float g_z[32 * 64];
__device__ __align__(128) uint4 g_mod[6144];
__device__ __align__(128) uint2 g_st[2 * SEQ * 8];
__device__ __align__(128) unsigned g_zflag[256];
__device__ __align__(128) unsigned g_kvflag[256];
__device__ __align__(128) unsigned g_aflag[16 * 64];
__device__ __align__(128) unsigned g_epoch[32];
__device__ unsigned g_done;
#define STAMP_C(id)
#define STAMP(id)
#define STAMP_T(id)
#define STAMP_W(id)

namespace {

__device__ __forceinline__ uint32_t smem_u32(const void* p) { return (uint32_t)__cvta_generic_to_shared(p); }
__device__ __forceinline__ void bail() { asm volatile("st.global.u32 [%0], %1;" :: "l"(0ull), "r"(0u) : "memory"); }
__device__ __forceinline__ void mbar_arrive(uint32_t bar) { asm volatile("mbarrier.arrive.shared::cta.b64 _, [%0];" :: "r"(bar) : "memory"); }
__device__ __forceinline__ void mbar_arrive_cta(uint32_t bar, uint32_t cta) {
  asm volatile("{\n.reg .b32 ra;\nmapa.shared::cluster.u32 ra, %0, %1;\nmbarrier.arrive.shared::cluster.b64 _, [ra];\n}" :: "r"(bar), "r"(cta) : "memory");
}
__device__ __forceinline__ void mbar_wait(uint32_t bar, uint32_t parity) {
  asm volatile("{\n.reg .pred p;\n.reg .u32 n;\nmov.u32 n, 0;\n"
               "W: .pragma \"nounroll\";\nmbarrier.try_wait.parity.shared::cta.b64 p, [%0], %1;\n@p bra.uni D;\n"
               "add.u32 n, n, 1;\nsetp.lt.u32 p, n, 4194304;\n@p bra.uni W;\nst.global.u32 [%2], n;\nD:\n}" :: "r"(bar), "r"(parity), "l"(0ull) : "memory");
}
#define ELECT "{\n.reg .pred e;\nelect.sync _|e, 0xffffffff;\n"
__device__ __forceinline__ void mbar_init_e(uint32_t bar, uint32_t cnt) { asm volatile(ELECT "@e mbarrier.init.shared::cta.b64 [%0], %1;\n}" :: "r"(bar), "r"(cnt) : "memory"); }
__device__ __forceinline__ void mbar_arrive_e(uint32_t bar) { asm volatile(ELECT "@e mbarrier.arrive.shared::cta.b64 _, [%0];\n}" :: "r"(bar) : "memory"); }
__device__ __forceinline__ void tma_a_e(uint32_t dst, const CUtensorMap* tm, int c0, int c1, uint32_t bar) {
  asm volatile(ELECT "@e mbarrier.arrive.expect_tx.shared::cta.b64 _, [%2], 16384;\n"
               "@e cp.async.bulk.tensor.2d.shared::cluster.global.mbarrier::complete_tx::bytes.multicast::cluster [%0], [%1, {%3, %4}], [%2], %5;\n}"
    :: "r"(dst), "l"(tm), "r"(bar), "r"(c0), "r"(c1), "h"((uint16_t)3) : "memory");
}
__device__ __forceinline__ void tma_b_e(uint32_t dst, const CUtensorMap* tm, int c0, int c1, int c2, uint32_t bar, uint32_t bytes) {
  asm volatile(ELECT "@e mbarrier.arrive.expect_tx.shared::cta.b64 _, [%2], %6;\n"
               "@e cp.async.bulk.tensor.3d.shared::cluster.global.mbarrier::complete_tx::bytes [%0], [%1, {%3, %4, %5}], [%2];\n}"
    :: "r"(dst), "l"(tm), "r"(bar), "r"(c0), "r"(c1), "r"(c2), "r"(bytes) : "memory");
}
__device__ __forceinline__ void tma_x_e(uint32_t dst, const CUtensorMap* tm, int c0, int c1, uint32_t bar) {
  asm volatile(ELECT "@e mbarrier.arrive.expect_tx.shared::cta.b64 _, [%2], 32768;\n"
               "@e cp.async.bulk.tensor.2d.shared::cluster.global.mbarrier::complete_tx::bytes [%0], [%1, {%3, %4}], [%2];\n"
               "@e cp.async.bulk.tensor.2d.shared::cluster.global.mbarrier::complete_tx::bytes [%5], [%1, {%6, %4}], [%2];\n}"
    :: "r"(dst), "l"(tm), "r"(bar), "r"(c0), "r"(c1), "r"(dst + 16384), "r"(c0 + 64) : "memory");
}
__device__ __forceinline__ void dsmem_copy_e(uint32_t dst, uint32_t src, uint32_t bar, uint32_t cta) {
  asm volatile(ELECT ".reg .b32 rd, rb;\nmapa.shared::cluster.u32 rd, %0, %3;\nmapa.shared::cluster.u32 rb, %2, %3;\n"
               "@e mbarrier.arrive.expect_tx.shared::cta.b64 _, [%2], 16384;\n"
               "@e cp.async.bulk.shared::cluster.shared::cta.mbarrier::complete_tx::bytes [rd], [%1], 16384, [rb];\n}"
               :: "r"(dst), "r"(src), "r"(bar), "r"(cta) : "memory");
}
__device__ __forceinline__ bool elect_one() {
  uint32_t p;
  asm volatile("{\n.reg .pred P;\nelect.sync _|P, 0xffffffff;\nselp.u32 %0, 1, 0, P;\n}" : "=r"(p));
  return p;
}
__device__ __forceinline__ void tma_st(const CUtensorMap* tm, uint32_t src, int c0, int c1) {
  asm volatile("cp.async.bulk.tensor.2d.global.shared::cta.bulk_group [%0, {%2, %3}], [%1];" :: "l"(tm), "r"(src), "r"(c0), "r"(c1) : "memory");
}
__device__ __forceinline__ void tma_prefetch3(const CUtensorMap* tm, int c0, int c1, int c2) {
  asm volatile("cp.async.bulk.prefetch.tensor.3d.L2.global [%0, {%1, %2, %3}];" :: "l"(tm), "r"(c0), "r"(c1), "r"(c2) : "memory");
}
__device__ __forceinline__ void bulk_prefetch(const void* p, uint32_t bytes) {
  asm volatile("cp.async.bulk.prefetch.L2.global [%0], %1;" :: "l"(p), "r"(bytes) : "memory");
}
__device__ __forceinline__ void bulk_commit() { asm volatile("cp.async.bulk.commit_group;" ::: "memory"); }
__device__ __forceinline__ void bulk_wait() { asm volatile("cp.async.bulk.wait_group 0;" ::: "memory"); }
__device__ __forceinline__ void fence_async_smem() { asm volatile("fence.proxy.async.shared::cta;" ::: "memory"); }
__device__ __forceinline__ void fence_async_global() { asm volatile("fence.proxy.async.global;" ::: "memory"); }
__device__ __forceinline__ void wg_fence() { asm volatile("wgmma.fence.sync.aligned;" ::: "memory"); }
__device__ __forceinline__ void wg_commit() { asm volatile("wgmma.commit_group.sync.aligned;" ::: "memory"); }
template <int N> __device__ __forceinline__ void wg_wait() { asm volatile("wgmma.wait_group.sync.aligned %0;" :: "n"(N) : "memory"); }
template <int N> __device__ __forceinline__ void fence_regs(float (&r)[N]) {
#pragma unroll
  for (int i = 0; i < N; i++) asm volatile("" : "+f"(r[i]) :: "memory");
}
template <int N> __device__ __forceinline__ void zero_regs(float (&r)[N]) {
#pragma unroll
  for (int i = 0; i < N; i++) asm volatile("mov.b32 %0, 0;" : "=f"(r[i]));
}
template <int N> __device__ __forceinline__ void zero_regs(uint32_t (&r)[N]) {
#pragma unroll
  for (int i = 0; i < N; i++) asm volatile("mov.b32 %0, 0;" : "=r"(r[i]));
}
__device__ __forceinline__ void mma16816(float (&d)[4], uint32_t a0, uint32_t a1, uint32_t a2, uint32_t a3, uint32_t b0, uint32_t b1) {
  asm volatile("mma.sync.aligned.m16n8k16.row.col.f32.bf16.bf16.f32 {%0, %1, %2, %3}, {%4, %5, %6, %7}, {%8, %9}, {%0, %1, %2, %3};"
               : "+f"(d[0]), "+f"(d[1]), "+f"(d[2]), "+f"(d[3]) : "r"(a0), "r"(a1), "r"(a2), "r"(a3), "r"(b0), "r"(b1));
}
__device__ __forceinline__ void cluster_arrive() { asm volatile("barrier.cluster.arrive.relaxed.aligned;" ::: "memory"); }
__device__ __forceinline__ void cluster_wait() { asm volatile("barrier.cluster.wait.acquire.aligned;" ::: "memory"); }
__device__ __forceinline__ void bar_sync(int id, int n) { asm volatile("bar.sync %0, %1;" :: "r"(id), "r"(n) : "memory"); }
__device__ __forceinline__ void bar_arrive(int id, int n) { asm volatile("bar.arrive %0, %1;" :: "r"(id), "r"(n) : "memory"); }
template <int R> __device__ __forceinline__ void reg_inc() { asm volatile("setmaxnreg.inc.sync.aligned.u32 %0;" :: "n"(R)); }
template <int R> __device__ __forceinline__ void reg_dec() { asm volatile("setmaxnreg.dec.sync.aligned.u32 %0;" :: "n"(R)); }
__device__ __forceinline__ void ldsm4(uint32_t addr, uint32_t& a, uint32_t& b, uint32_t& c, uint32_t& d) {
  asm volatile("ldmatrix.sync.aligned.m8n8.x4.shared.b16 {%0, %1, %2, %3}, [%4];" : "=r"(a), "=r"(b), "=r"(c), "=r"(d) : "r"(addr) : "memory");
}
__device__ __forceinline__ void stsm4(uint32_t addr, uint32_t a, uint32_t b, uint32_t c, uint32_t d) {
  asm volatile("stmatrix.sync.aligned.m8n8.x4.shared.b16 [%0], {%1, %2, %3, %4};" :: "r"(addr), "r"(a), "r"(b), "r"(c), "r"(d) : "memory");
}
__device__ __forceinline__ void stsm4_if(uint32_t addr, uint32_t a, uint32_t b, uint32_t c, uint32_t d, int on) {
  asm volatile("{\n.reg .pred q;\nsetp.ne.s32 q, %5, 0;\n@q stmatrix.sync.aligned.m8n8.x4.shared.b16 [%0], {%1, %2, %3, %4};\n}"
               :: "r"(addr), "r"(a), "r"(b), "r"(c), "r"(d), "r"(on) : "memory");
}
__device__ __forceinline__ uint4 lds128(uint32_t addr) {
  uint4 v; asm volatile("ld.shared.v4.u32 {%0, %1, %2, %3}, [%4];" : "=r"(v.x), "=r"(v.y), "=r"(v.z), "=r"(v.w) : "r"(addr) : "memory"); return v;
}
__device__ __forceinline__ uint32_t lds32(uint32_t addr) { uint32_t v; asm volatile("ld.shared.u32 %0, [%1];" : "=r"(v) : "r"(addr) : "memory"); return v; }
__device__ __forceinline__ void sts16(uint32_t addr, uint32_t v) { asm volatile("st.shared.u16 [%0], %1;" :: "r"(addr), "h"((uint16_t)v) : "memory"); }
__device__ __forceinline__ void sts32(uint32_t addr, uint32_t v) { asm volatile("st.shared.u32 [%0], %1;" :: "r"(addr), "r"(v) : "memory"); }
__device__ __forceinline__ void sts128(uint32_t addr, uint4 v) { asm volatile("st.shared.v4.u32 [%0], {%1, %2, %3, %4};" :: "r"(addr), "r"(v.x), "r"(v.y), "r"(v.z), "r"(v.w) : "memory"); }
__device__ __forceinline__ uint32_t pack2(float lo, float hi) { uint32_t r; asm("cvt.rn.bf16x2.f32 %0, %1, %2;" : "=r"(r) : "f"(hi), "f"(lo)); return r; }
__device__ __forceinline__ uint32_t pack2_relu(float lo, float hi) { uint32_t r; asm("cvt.rn.relu.bf16x2.f32 %0, %1, %2;" : "=r"(r) : "f"(hi), "f"(lo)); return r; }
__device__ __forceinline__ float bf_lo(uint32_t v) { return __uint_as_float(v << 16); }
__device__ __forceinline__ float bf_hi(uint32_t v) { return __uint_as_float(v & 0xffff0000u); }
__device__ __forceinline__ uint32_t fma2(uint32_t a, uint32_t b, uint32_t c) { uint32_t r; asm("fma.rn.bf16x2 %0, %1, %2, %3;" : "=r"(r) : "r"(a), "r"(b), "r"(c)); return r; }
__device__ __forceinline__ uint32_t mul2(uint32_t a, uint32_t b) { uint32_t r; asm("mul.rn.bf16x2 %0, %1, %2;" : "=r"(r) : "r"(a), "r"(b)); return r; }
__device__ __forceinline__ uint32_t max2(uint32_t a, uint32_t b) { uint32_t r; asm("max.bf16x2 %0, %1, %2;" : "=r"(r) : "r"(a), "r"(b)); return r; }
__device__ __forceinline__ uint32_t min2(uint32_t a, uint32_t b) { uint32_t r; asm("min.bf16x2 %0, %1, %2;" : "=r"(r) : "r"(a), "r"(b)); return r; }
__device__ __forceinline__ float ex2(float x) { float r; asm("ex2.approx.ftz.f32 %0, %1;" : "=f"(r) : "f"(x)); return r; }
__device__ __forceinline__ float rcp(float x) { float r; asm("rcp.approx.ftz.f32 %0, %1;" : "=f"(r) : "f"(x)); return r; }
__device__ __forceinline__ uint4 ldg_nc(const void* p) {
  uint4 v; asm volatile("ld.global.nc.L1::no_allocate.v4.u32 {%0, %1, %2, %3}, [%4];" : "=r"(v.x), "=r"(v.y), "=r"(v.z), "=r"(v.w) : "l"(p)); return v;
}
__device__ __forceinline__ uint4 ld_relaxed_v4(const void* p) {
  uint64_t a, b; asm volatile("ld.relaxed.gpu.global.v2.b64 {%0, %1}, [%2];" : "=l"(a), "=l"(b) : "l"(p) : "memory");
  return make_uint4((uint32_t)a, (uint32_t)(a >> 32), (uint32_t)b, (uint32_t)(b >> 32));
}
__device__ __forceinline__ void st_relaxed_v2(void* p, uint32_t lo, uint32_t hi) {
  uint64_t a = (uint64_t)lo | ((uint64_t)hi << 32);
  asm volatile("st.relaxed.gpu.global.b64 [%0], %1;" :: "l"(p), "l"(a) : "memory");
}
__device__ __forceinline__ void st_relaxed(void* p, uint32_t v) { asm volatile("st.relaxed.gpu.global.u32 [%0], %1;" :: "l"(p), "r"(v) : "memory"); }
__device__ __forceinline__ unsigned ld_acquire(const unsigned* p) { unsigned v; asm volatile("ld.acquire.gpu.global.u32 %0, [%1];" : "=r"(v) : "l"(p) : "memory"); return v; }
__device__ __forceinline__ void st_release(unsigned* p, unsigned v) { asm volatile("st.release.gpu.global.u32 [%0], %1;" :: "l"(p), "r"(v) : "memory"); }
__device__ __forceinline__ unsigned flags_wait(const unsigned* p, unsigned e, unsigned need) {
  unsigned m;
  uint32_t n = 0;
#pragma unroll 1
  do {
    m = __ballot_sync(0xffffffffu, ld_acquire(p) == e);
    if (++n > (1u << 21)) { bail(); break; }
  } while ((m & need) != need);
  return m;
}
__device__ __forceinline__ float4 ldcg4(const float* p) {
  float4 v; asm volatile("ld.global.cg.v4.f32 {%0, %1, %2, %3}, [%4];" : "=f"(v.x), "=f"(v.y), "=f"(v.z), "=f"(v.w) : "l"(p) : "memory"); return v;
}
__device__ __forceinline__ void red4(float* p, const float* a) {
  asm volatile("red.global.add.v4.f32 [%0], {%1, %2, %3, %4};" :: "l"(p), "f"(a[0]), "f"(a[1]), "f"(a[2]), "f"(a[3]) : "memory");
}
__device__ __forceinline__ void red1(float* p, float a) { asm volatile("red.global.add.f32 [%0], %1;" :: "l"(p), "f"(a) : "memory"); }
__device__ __forceinline__ float silu(float v) { return __fdividef(v, 1.0f + __expf(-v)); }
__device__ __forceinline__ uint32_t tagged(float v, uint32_t tag) { return (__float_as_uint(v) & 0xffffff00u) | tag; }

constexpr float LOG2E = 1.4426950408889634f;

__device__ __forceinline__ void feature_map(const float (&p)[2][16], uint32_t (&f)[2][16], bool norm) {
  float ep[2][16], em[2][16];
#pragma unroll
  for (int u = 0; u < 2; u++) {
    uint32_t k[8];
#pragma unroll
    for (int i = 0; i < 8; i++) k[i] = pack2(p[u][2 * i], p[u][2 * i + 1]);
    const uint32_t x0 = max2(max2(k[0], k[2]), max2(k[4], k[6])), x1 = max2(max2(k[1], k[3]), max2(k[5], k[7]));
    const uint32_t n0 = min2(min2(k[0], k[2]), min2(k[4], k[6])), n1 = min2(min2(k[1], k[3]), min2(k[5], k[7]));
    uint32_t mx = max2(__byte_perm(x0, x1, 0x5410), __byte_perm(x0, x1, 0x7632)), mn = min2(__byte_perm(n0, n1, 0x5410), __byte_perm(n0, n1, 0x7632));
    mx = max2(mx, __shfl_xor_sync(0xffffffffu, mx, 1)); mn = min2(mn, __shfl_xor_sync(0xffffffffu, mn, 1));
    mx = max2(mx, __shfl_xor_sync(0xffffffffu, mx, 2)); mn = min2(mn, __shfl_xor_sync(0xffffffffu, mn, 2));
    const float mxl[2] = {-bf_lo(mx) * LOG2E, -bf_hi(mx) * LOG2E}, mnl[2] = {bf_lo(mn) * LOG2E, bf_hi(mn) * LOG2E};
#pragma unroll
    for (int i = 0; i < 16; i++) {
      const float v = (i & 1) ? bf_hi(k[i >> 1]) : bf_lo(k[i >> 1]);
      ep[u][i] = ex2(fmaf(v, LOG2E, mxl[(i >> 1) & 1]));
      em[u][i] = ex2(fmaf(v, -LOG2E, mnl[(i >> 1) & 1]));
    }
  }
  if (norm) {
#pragma unroll
    for (int ur = 0; ur < 4; ur++) {
      float* a = &ep[ur >> 1][2 * (ur & 1)];
      float* b = &em[ur >> 1][2 * (ur & 1)];
      __half2 s = __floats2half2_rn(((a[0] + a[1]) + (a[4] + a[5])) + ((a[8] + a[9]) + (a[12] + a[13])),
                                    ((b[0] + b[1]) + (b[4] + b[5])) + ((b[8] + b[9]) + (b[12] + b[13])));
      s = __hadd2(s, __shfl_xor_sync(0xffffffffu, s, 1));
      const float2 t = __half22float2(s), v = __half22float2(__shfl_xor_sync(0xffffffffu, s, 2));
      const float sp = rcp(t.x + v.x), sm = rcp(t.y + v.y);
#pragma unroll
      for (int i = 0; i < 8; i++) { a[(i >> 1) * 4 + (i & 1)] *= sp; b[(i >> 1) * 4 + (i & 1)] *= sm; }
    }
  }
#pragma unroll
  for (int u = 0; u < 2; u++)
#pragma unroll
    for (int i = 0; i < 8; i++) { f[u][i] = pack2(ep[u][2 * i], ep[u][2 * i + 1]); f[u][8 + i] = pack2(em[u][2 * i], em[u][2 * i + 1]); }
}
template <int BN> __device__ __forceinline__ void mma_ss(float (&d)[BN / 2], uint64_t da, uint64_t db, int sd);
template <> __device__ __forceinline__ void mma_ss<128>(float (&d)[64], uint64_t da, uint64_t db, int sd) { wgmma_ss_n128(d, da, db, sd); }
template <> __device__ __forceinline__ void mma_ss<192>(float (&d)[96], uint64_t da, uint64_t db, int sd) { wgmma_ss_n192(d, da, db, sd); }
__device__ __forceinline__ uint64_t mkdesc(uint32_t lo, uint32_t hi) { return (uint64_t)lo | ((uint64_t)hi << 32); }
constexpr uint32_t DHI_SW = 0x40000040u;

__device__ __forceinline__ void release(uint32_t bar, int lane) {
  if (lane < 2 && bar) mbar_arrive_cta(bar, lane);
}
__device__ __forceinline__ void staged_arrive(uint32_t sb, int n) {
  fence_async_smem();
  __syncwarp();
  mbar_arrive_e(sb + OFF_BAR + (B_STG + n) * 8);
}
template <int N> __device__ __forceinline__ void load_vec(uint32_t (&v)[N], uint32_t vec) {
  const uint32_t vb = vec + (threadIdx.x & 3) * (N * 4);
#pragma unroll
  for (int g = 0; g < N / 4; g++) {
    const uint4 q = lds128(vb + g * 16);
    v[4 * g] = q.x; v[4 * g + 1] = q.y; v[4 * g + 2] = q.z; v[4 * g + 3] = q.w;
  }
}
template <int BN> __device__ __forceinline__ void init_bias(float (&acc)[2][BN / 2], uint32_t vec) {
  uint32_t v[BN / 8];
  load_vec(v, vec);
#pragma unroll
  for (int g = 0; g < BN / 8; g++) {
    acc[0][4 * g] = acc[0][4 * g + 2] = acc[1][4 * g] = acc[1][4 * g + 2] = bf_lo(v[g]);
    acc[0][4 * g + 1] = acc[0][4 * g + 3] = acc[1][4 * g + 1] = acc[1][4 * g + 3] = bf_hi(v[g]);
  }
  fence_regs(acc[0]); fence_regs(acc[1]);
}

template <int BN>
__device__ __forceinline__ void mainloop(float (&acc)[2][BN / 2], uint32_t sb, int T, int nl) {
  constexpr int STRIDE = (BN == 128 ? 32768 : 40960) >> 4, NS = BN == 128 ? 5 : 4;
  const int lane = threadIdx.x & 31;
  const uint32_t d0 = (sb & 0x3FFFF) >> 4, f0 = sb + OFF_BAR + (BN == 128 ? B_FULL : B_FULL2) * 8;
  const int nk = T == 7 ? 56 : 16;
  uint32_t fb = f0, st = d0, par = 0, prev = 0;
  if (BN == 128) {
    fb += ((0x10403210u >> (4 * T)) & 7) * 8; st += ((0x21003210u >> (4 * T)) & 7) * STRIDE; par = (0x8Au >> T) & 1;
  }
#pragma unroll 1
  for (int n = 0; n < nk; n++) {
    const uint32_t da = ((unsigned)(n - nl) < 2u ? d0 + (OFF_E0 >> 4) + (n - nl) * 1024 : st) | 0x10000u, db = (st + 1024) | 0x2000000u;
    mbar_wait(fb, par);
    if (n == 15 && T != 7) bar_arrive(1 + (T & 1), 256);
    wg_fence();
#pragma unroll
    for (int ks = 0; ks < 4; ks++)
#pragma unroll
      for (int mb = 0; mb < 2; mb++) mma_ss<BN>(acc[mb], mkdesc(da + mb * 512 + ks * 2, DHI_SW), mkdesc(db + ks * 128, DHI_SW), 1);
    wg_commit();
    wg_wait<1>();
    release(prev, lane);
    prev = (BN == 192 && n >= 12) ? sb + OFF_BAR + (n == 12 ? B_EMPTY + 4 : B_EMPTY + n - 13) * 8 : fb + 40;
    fb += 8; st += STRIDE;
    if (fb == f0 + NS * 8) { fb = f0; par ^= 1; }
    if (st == d0 + NS * STRIDE) st = d0;
  }
  wg_wait<0>();
  release(prev, lane);
  if (BN == 192) release(prev + 8, lane);
  fence_regs(acc[0]); fence_regs(acc[1]);
}

template <int BN>
__device__ __forceinline__ void epilogue_f1(float (&acc)[2][BN / 2], uint32_t stbase, uint32_t x0) {
#pragma unroll
  for (int j2 = 0; j2 < BN / 16; j2++)
#pragma unroll
    for (int mb = 0; mb < 2; mb++) {
      uint32_t o[4];
#pragma unroll
      for (int q = 0; q < 4; q++) {
        const uint32_t r = pack2_relu(acc[mb][8 * j2 + 2 * q], acc[mb][8 * j2 + 2 * q + 1]);
        o[q] = mul2(r, r);
      }
      stsm4(stbase + mb * 8192 + (j2 >> 2) * 16384 + (x0 ^ ((j2 & 3) << 5)), o[0], o[1], o[2], o[3]);
    }
}

__global__ void __cluster_dims__(2, 1, 1) __launch_bounds__(384, 1) fused_block_kernel(const __grid_constant__ Params p) {
  extern __shared__ __align__(1024) uint8_t smem_raw[];
  const uint32_t sb = smem_u32(smem_raw);
  const int tid = threadIdx.x, lane = tid & 31, wid = __shfl_sync(0xffffffffu, tid >> 5, 0), wg = wid >> 2;
  const int b = blockIdx.x;
  const int rank = b & 1, rb = b >> 3, j = b & 7;
  const int row0 = rb * 128;
  const uint32_t bars = sb + OFF_BAR;
  if (tid == 0) STAMP(0);
  if (wg == 0) {
    reg_dec<40>();
    unsigned e;
    asm volatile("ld.relaxed.gpu.global.u32 %0, [%1];" : "=r"(e) : "l"(&g_epoch[lane]) : "memory");
    if (wid == 3) {
      mbar_init_e(bars + B_XBAR * 8, 1);
      fence_async_smem();
      tma_x_e(sb + OFF_E0, &p.t_x, 128 * j, row0, bars + B_XBAR * 8);
    }
#pragma unroll 1
    for (int i = wid; i < B_XBAR; i += 4)
      mbar_init_e(bars + i * 8, i >= B_EFREE ? 1 : i >= B_STG ? (i == B_STG + S_O || i == B_STG + S_O0 ? 8 : 4) : 1 << (((0x3fc55ffd55ull >> (2 * i))) & 3));
    asm volatile("fence.mbarrier_init.release.cluster;" ::: "memory");
    if (wid == 3) { sts32(bars + 384, (e + 1) & 255); __threadfence_block(); }
    __syncwarp();
    cluster_arrive();
    e += 1;
    if (wid < 2) {
      const unsigned* flags = g_aflag + rb * 64 + lane;
      unsigned mask = 0;
      uint32_t f0 = bars, fend = bars + 40, fb = bars, dst = sb, stride = 32768, par = 1;
      cluster_wait();
#pragma unroll 1
      for (int sg = 0; sg < 11; sg++) {
        const int ksize = sg == 8 ? 1536 : 1024, kbase = sg == 4 ? 64 : sg < 9 ? 0 : 1024 * sg - 7680;
        const int nloc = ((0x31 >> sg) & 1) * 4, nstep = sg == 3 ? 6 : sg == 4 ? 10 : ksize >> 6, kinc = (sg == 3 || sg == 4) ? 128 : 64;
        int ko = ((sg == 3 ? j + 2 : j) & 6) * (ksize >> 3);
        if (sg == 5) {
          mbar_wait(bars + (B_EMPTY + 3) * 8, 0);
          fb = f0 = bars + B_FULL2 * 8; fend = f0 + 32; dst = sb; stride = 40960; par = 1;
        } else if (sg == 6) {
          f0 = bars; fend = bars + 40; fb = bars + 32; dst = sb; stride = 32768; par = 0;
        }
        if (wid == 0) {
          const CUtensorMap* tm = &p.a_h + (sg >= 8 ? 2 : kinc >> 7);
          const int fbase = (0x24a9c0 >> (2 * sg) & 3) * 8, fmul = sg == 8 ? 342 : 512;
          if (sg == 8) mask = 0;
#pragma unroll 1
          for (int n = 0; n < nstep; n++) {
            if (n < nloc) {
              mbar_wait(fb + 40, par);
              mbar_wait(bars + ((n < 2 ? B_STG : B_ISS) + (sg ? sg - 1 : 0)) * 8, 0);
              if (n < 2) mbar_arrive_e(fb);
              else dsmem_copy_e(dst, sb + OFF_E0 + (n - 2) * 16384, fb, rank ^ 1);
            } else {
              const unsigned need = 1u << (fbase + (ko * fmul >> 16));
              if (!(mask & need)) {
                if (sg == 4 || sg >= 8) { mbar_wait(bars + (sg == 10 ? B_RLY : B_EFREE + (sg >> 2)) * 8, 0); mask = sg == 10 ? ~0u : 0xffffu; }
                else mask = flags_wait(flags, e, need);
                fence_async_global();
                if (sg < 9) STAMP_W(32 + sg);
              }
              mbar_wait(fb + 40, par);
              tma_a_e(dst + rank * 8192, tm, kbase + ko, row0 + rank * 64, fb);
              if (n == 8 && sg == 4) {
                mbar_wait(bars + (B_EFREE + S_O) * 8, 0);
                tma_x_e(sb + OFF_E0, &p.t_x, 128 * j, row0, bars + B_XBAR * 8);
              }
              if (n == 8 && sg == 0) mbar_arrive_e(bars + (B_ISS + 1) * 8);
            }
            ko += n < nloc ? 64 : kinc; fb += 8; dst += stride;
            if (ko == ksize) ko = 0;
            if (fb == fend) { fb = f0; par ^= 1; }
            if (dst == sb + RING) dst = sb;
          }
        } else {
          const CUtensorMap* tm = &p.b_kv + ((0x55544322100ull >> (4 * sg)) & 7);
          const int c0 = sg < 2 ? 128 * j + 64 * sg : 0;
          const int c2 = sg < 2 ? 1 : sg == 5 ? 3 * j : 2 * j + (sg == 6 ? 24 : sg == 7 ? 40 : 0);
#pragma unroll 1
          for (int n = 0; n < nstep; n++) {
            const int krow = n < nloc ? ko ^ (rank << 7) : kbase + ko;
            mbar_wait(fb + 40, par);
            tma_b_e(dst + 16384, tm, c0, krow, c2, fb, stride - 16384);
            if (krow == 64 * rb && sg < 8) {
              if (sg == 1 && lane < 8) bulk_prefetch(p.wmod + (size_t)(8 * b + lane) * 6144 + 4096, 4096);
              if (elect_one()) {
                if (sg != 7 || rb < 8)
                  tma_prefetch3(&p.b_kv + ((0x55444210u >> (4 * sg)) & 7), sg ? 0 : c0 + 64, krow + (sg > 5 ? 2048 * sg - 11264 : 0),
                                sg ? 2 * j + (sg == 5 ? 40 : sg == 3 || sg == 4 ? 24 : 0) : 1);
                if ((0x64 >> sg) & 1) tma_prefetch3(sg == 2 ? &p.b_w1x : &p.b_w2, 0, krow + (sg == 6 ? 2048 : 0), sg == 2 ? 3 * j : 2 * j);
              }
              __syncwarp();
            }
            ko += n < nloc ? 64 : kinc; fb += 8; dst += stride;
            if (ko == ksize) ko = 0;
            if (fb == fend) { fb = f0; par ^= 1; }
            if (dst == sb + RING) dst = sb;
          }
        }
      }
    } else if (wid == 2) {
      float4* kz = reinterpret_cast<float4*>(g_kv) + j * 2048 + rb * 128;
#pragma unroll
      for (int u = 0; u < 4; u++) kz[lane + u * 32] = make_float4(0.f, 0.f, 0.f, 0.f);
      if (lane < 4) reinterpret_cast<float4*>(g_z)[j * 64 + rb * 4 + lane] = make_float4(0.f, 0.f, 0.f, 0.f);
      __syncwarp();
      if (lane == 0) st_release(&g_zflag[j * 32 + rb], e);
      __syncwarp();
      cluster_wait();
      mbar_wait(bars + B_XBAR * 8, 0);
      if (elect_one()) {
        tma_prefetch3(&p.b_kv, 128 * j, 64 * rb, 1);
      }
#pragma unroll 4
      for (int u = 0; u < 16; u++) {
        const int pc = lane + u * 32;
        const uint4 v = ldg_nc(p.wphi + (size_t)j * 4096 + pc * 8);
        const int d = (pc >> 2) & 31;
        sts128(sb + OFF_WPHI + (pc >> 7) * 2048 + (d >> 3) * 512 + (pc & 3) * 128 + (d & 7) * 16, v);
      }
#pragma unroll 1
      for (int u = lane; u < 72; u += 32) {
        const int v = u >> 4, g = u < 48 ? u & 15 : u - 48;
        const uint4 q = ldg_nc(v == 0 ? p.b2 + 128 * j + 8 * g : p.b1 + (v < 3 ? 512 + 1024 * v + 128 * j : 192 * j) + 8 * g);
        const uint32_t a = sb + OFF_VEC + 1792 + (v < 3 ? v : 3) * 256 + g * 4, s = v < 3 ? 64 : 96;
        sts32(a, q.x); sts32(a + s, q.y); sts32(a + 2 * s, q.z); sts32(a + 3 * s, q.w);
      }
      __syncwarp();
      flags_wait(&g_zflag[j * 32 + lane], e, 0xffffu);
      fence_async_smem();
      __syncwarp();
      mbar_arrive_e(bars + B_INIT * 8);
      mbar_wait(bars + (B_STG + S_KV) * 8, 0);
      {
        unsigned d = 0;
        if (lane == 0) d = atomicAdd(&g_done, 1u);
        if (__shfl_sync(0xffffffffu, d, 0) == 127u) { g_done = 0; g_epoch[lane] = e; }
      }
      flags_wait(&g_kvflag[j * 32 + lane], e, 0xffffu);
      mbar_arrive_e(bars + B_KVOK * 8);
      flags_wait(&g_kvflag[j * 32 + lane], e, 0xffff0000u);
      mbar_arrive_e(bars + B_KVOK * 8 + 8);
      STAMP_W(29);
      flags_wait(g_aflag + rb * 64 + lane, e, 0xff00u);
      mbar_arrive_e(bars + (B_EFREE + 1) * 8);
      mbar_wait(bars + (B_EFREE + 6) * 8, 0);
      flags_wait(g_aflag + rb * 64 + 32 + lane, e, 0xffffu);
      mbar_arrive_e(bars + (B_EFREE + 2) * 8);
      mbar_wait(bars + (B_EFREE + 7) * 8, 0);
      flags_wait(g_aflag + rb * 64 + 32 + lane, e, 0xff0000u);
      mbar_arrive_e(bars + B_RLY * 8);
    } else {
      cluster_wait();
      if (elect_one()) {
#pragma unroll 1
        for (int i = 0; i < 10; i++) {
          const int ev = i == 3 ? S_O0 : i - (i > 3);
          const CUtensorMap* tm = &p.t_h + ((0x1322201000ull >> (4 * ev)) & 3);
          const int col = ev == S_F1 ? 192 * j : 128 * j + (ev == 6 ? 1536 : ev == 7 ? 2560 : 0);
          mbar_wait(bars + (B_STG + ev) * 8, 0);
          if (ev == 1 || ev == 2) {
            st_release(&g_kvflag[j * 32 + (ev - 1) * 16 + rb], e);
          } else {
            if (ev >= S_F1 && ev < 8) {
#pragma unroll 1
              for (int u = 0; u < (ev == S_F1 ? 6 : 4); u++) {
                tma_st(&p.a_h1, sb + OFF_E0 + u * 8192, col + (u >> 1) * 64, row0 + (u & 1) * 64);
                __nanosleep(PACE);
              }
            } else {
              if (ev != S_O) tma_st(tm, sb + OFF_E0, col, row0);
              if (ev != S_O0) tma_st(tm, sb + OFF_E0 + 16384, col + 64, row0);
            }
            bulk_commit();
            if (ev < S_F1) mbar_arrive(bars + (B_ISS + ev) * 8);
            bulk_wait();
            st_relaxed(g_aflag + rb * 64 + ((0x3765421000ull >> (4 * ev)) & 7) * 8 + j, e);
            mbar_arrive(bars + (B_EFREE + ev) * 8);
          }
          STAMP(ev == 9 ? 43 : 44 + ev);
        }
      }
    }
    __syncwarp();
    cluster_arrive(); cluster_wait();
  } else {
    cluster_arrive();
    reg_inc<232>();
    const int t = tid & 127, w = wid & 3, ab = wg - 1;
    const uint32_t srow = w * 16 + (lane & 7) + ((lane >> 3) & 1) * 8;
    const uint32_t stbase = sb + OFF_E0 + srow * 128;
    const uint32_t x0 = ((lane >> 4) ^ (lane & 7)) << 4;
    const uint32_t d0 = (sb & 0x3FFFF) >> 4;
    uint32_t prog = ab ? 03334313u : 0352213321u;
    int T = -ab, gi = ab;
    uint32_t xr[2][32];
    zero_regs(xr[0]); zero_regs(xr[1]);
#pragma unroll 1
    for (; prog; prog >>= 3) {
      const int op = prog & 7;
      if (op == 1) {
        if (ab) mbar_wait(bars + (B_ISS + 1) * 8, 0);
        else if (gi *= 2) __nanosleep(300);
        const int col = 2048 * gi + 64 * (b & 31), r0 = (b >> 5) * 256 + w * 64;
        const bf16* wp = p.wmod + (size_t)(r0 + 2 * (lane & 3)) * 6144 + col + 2 * (lane & 28);
        uint4 wv[16];
#pragma unroll
        for (int u = 0; u < 16; u++) wv[u] = ldg_nc(wp + ((u >> 1) * 8 + (u & 1)) * 6144);
        if (!gi) {
          const uint32_t cw = __ldg(reinterpret_cast<const unsigned*>(p.c + r0) + lane);
          const uint32_t cs = pack2(silu(bf_lo(cw)), silu(bf_hi(cw))), a = sb + OFF_RED + 1024 + (lane >> 2) * 256 + (lane & 3) * 32 + w * 4;
          sts32(a, cs & 0xffffu); sts32(a + 16, cs << 16); sts32(a + 128, cs >> 16); sts32(a + 144, cs & 0xffff0000u);
          fence_async_smem();
          cluster_wait();
          bar_sync(3, 128);
        }
        float s0[4], s1[4];
        zero_regs(s0); zero_regs(s1);
        wg_fence();
#pragma unroll
        for (int u = 0; u < 8; u++) {
          const uint64_t db = mkdesc((d0 + ((OFF_RED + 1024) >> 4) + u * 16) | 0x80000u, 8u);
          wgmma_rs_n8(s0, wv[2 * u].x, wv[2 * u].y, wv[2 * u + 1].x, wv[2 * u + 1].y, db, u);
          wgmma_rs_n8(s1, wv[2 * u].z, wv[2 * u].w, wv[2 * u + 1].z, wv[2 * u + 1].w, db, u);
        }
        wg_commit();
        wg_wait<0>();
        fence_regs(s0); fence_regs(s1);
        const uint32_t red = sb + OFF_RED, tag = lds32(bars + 384);
        if ((lane & 3) == w) {
          sts128(red + (t & 124) * 8, make_uint4(__float_as_uint(s0[0]), __float_as_uint(s0[1]), __float_as_uint(s0[2]), __float_as_uint(s0[3])));
          sts128(red + (t & 124) * 8 + 16, make_uint4(__float_as_uint(s1[0]), __float_as_uint(s1[1]), __float_as_uint(s1[2]), __float_as_uint(s1[3])));
        }
        bar_sync(3 + ab, 128);
        if (t < 64) {
          float v = 0.f;
#pragma unroll
          for (int q = 0; q < 4; q++) v += __uint_as_float(lds32(red + q * 256 + t * 4));
          st_relaxed(reinterpret_cast<unsigned*>(g_mod + col + t) + (b >> 5), tagged(v, tag));
        }
        STAMP_T(1 + gi);
        gi >>= 1;
      } else if (op == 2) {
        const uint4* src = g_mod + 2048 * gi + 128 * j + t;
        const uint32_t tag = lds32(bars + 384);
        uint32_t n = 0; uint4 v0, v1;
#pragma unroll 1
        while (true) {
          v0 = ld_relaxed_v4(src); v1 = ld_relaxed_v4(src + 1024);
          if (__all_sync(0xffffffffu, (((v0.x ^ tag) | (v0.y ^ tag) | (v0.z ^ tag) | (v0.w ^ tag) | (v1.x ^ tag) | (v1.y ^ tag) | (v1.z ^ tag) | (v1.w ^ tag)) & 255) == 0)) break;
          if (++n > (1u << 21)) { bail(); break; }
        }
        uint32_t m = pack2((__uint_as_float(v0.x) + __uint_as_float(v0.y)) + (__uint_as_float(v0.z) + __uint_as_float(v0.w)),
                           (__uint_as_float(v1.x) + __uint_as_float(v1.y)) + (__uint_as_float(v1.z) + __uint_as_float(v1.w)));
        m = fma2(m, 0x3f803f80u, gi == 0 ? 0x3f800000u : gi == 2 ? 0x3f80u : 0u);
        const uint32_t a = sb + OFF_VEC + 256 + gi * 512 + ((t >> 1) & 3) * 64 + (t >> 3) * 4 + (t & 1) * 2;
        sts16(a, m); sts16(a + 256, m >> 16);
        __syncwarp();
        STAMP_T(4 + gi);
        if (gi != 1) bar_arrive(5, 256);
        gi++;
      } else if (op != 5) {
        uint32_t(&af)[32] = xr[0];
        if (op == 3) {
          float acc[2][64];
          zero_regs(acc[0]); zero_regs(acc[1]);
          if (T >= 0) {
            if (T > 4) init_bias<128>(acc, sb + OFF_VEC + (T == 7 ? 1792 : 256 * T + 768));
            if (T) bar_sync(2 - ab, 256);
            mainloop<128>(acc, sb, T, T == 0 ? 0 : T == 3 ? 6 : 64);
            STAMP_T(9 + T);
            mbar_wait(bars + ((T == 1 || T == 2) ? B_STG + T : B_EFREE + T) * 8, 0);
          }
          T += 2;
          if ((T & 3) == 1) {
            const uint32_t vg = sb + OFF_VEC + 192 * T - 192;
#pragma unroll 1
            for (int pass = T > 1; pass < 2; pass++) {
              if (T != 9) {
                if (pass) {
                  if (T == 1) cluster_wait();
                  mbar_wait(bars + B_XBAR * 8, T >> 2);
                  if (T == 1) STAMP_T(8);
                }
#pragma unroll
                for (int i = 0; i < 16; i++)
                  ldsm4(stbase + (i >> 3) * 8192 + ((i >> 2) & 1) * 16384 + (x0 ^ ((i & 3) << 5)), xr[i >> 3][(i & 7) * 4], xr[i >> 3][(i & 7) * 4 + 1],
                        xr[i >> 3][(i & 7) * 4 + 2], xr[i >> 3][(i & 7) * 4 + 3]);
              }
              if (T > 1) {
                uint32_t g[16];
                if (T == 5) bar_sync(5, 256);
                load_vec(g, vg);
#pragma unroll
                for (int mb = 0; mb < 2; mb++)
#pragma unroll
                  for (int i = 0; i < 32; i++) xr[mb][i] = fma2(g[i >> 1], pack2(acc[mb][2 * i], acc[mb][2 * i + 1]), xr[mb][i]);
              }
              if (T != 9) {
                float s[4], q[4];
                const uint32_t tag = lds32(bars + 384);
#pragma unroll
                for (int mb = 0; mb < 2; mb++) {
                  float c1[4] = {0.f, 0.f, 0.f, 0.f}, g0[4] = {0.f, 0.f, 0.f, 0.f}, g1[4] = {0.f, 0.f, 0.f, 0.f};
#pragma unroll
                  for (int i = 0; i < 32; i += 4) {
                    const uint32_t* a = &xr[mb][i];
                    mma16816(c1, a[0], a[1], a[2], a[3], 0x3f803f80u, 0x3f803f80u);
                    mma16816(g0, a[0], a[1], a[2], a[3], a[0], a[2]);
                    mma16816(g1, a[0], a[1], a[2], a[3], a[1], a[3]);
                  }
                  s[2 * mb] = c1[0]; s[2 * mb + 1] = c1[2];
                  q[2 * mb] = __shfl_sync(0xffffffffu, (lane & 4) ? g0[1] : g0[0], lane >> 3, 4);
                  q[2 * mb + 1] = __shfl_sync(0xffffffffu, (lane & 4) ? g1[3] : g1[2], lane >> 3, 4);
                }
                s[0] = (lane & 2) ? ((lane & 1) ? s[3] : s[2]) : ((lane & 1) ? s[1] : s[0]);
                q[0] = (lane & 2) ? ((lane & 1) ? q[3] : q[2]) : ((lane & 1) ? q[1] : q[0]);
                uint2* st = g_st + ((T > 1 ? 16 : 0) + rb) * 1024 + (w * 16 + (lane >> 2) + (lane & 1) * 8 + (lane & 2) * 32) * 2;
                if (pass) st_relaxed_v2(st + (j >> 1) * 256 + rank, __float_as_uint(s[0] * (1.0f / 128.0f)), tagged(fmaxf(fmaf(s[0] * s[0], -1.0f / 128.0f, q[0]), 0.f), tag));
                STAMP_T(T > 1 ? 26 : 25);
#pragma unroll
                for (int mb = 0; mb < 2; mb++) {
#pragma unroll
                  for (int i = 0; i < 32; i++) { acc[mb][2 * i] = bf_lo(xr[mb][i]); acc[mb][2 * i + 1] = bf_hi(xr[mb][i]); }
                  fence_regs(acc[mb]);
                }
                uint4 v[4] = {};
                uint32_t n = 0;
#pragma unroll 1
                while (pass) {
                  uint32_t bad = 0;
#pragma unroll
                  for (int u = 0; u < 4; u++) v[u] = ld_relaxed_v4(st + u * 256);
#pragma unroll
                  for (int u = 0; u < 4; u++) bad |= (v[u].y ^ tag) | (v[u].w ^ tag);
                  if (__all_sync(0xffffffffu, (bad & 255) == 0)) break;
                  if (++n > (1u << 21)) { bail(); break; }
                }
                float m = 0.f, var = 0.f;
#pragma unroll
                for (int u = 0; u < 4; u++) m += __uint_as_float(v[u].x) + __uint_as_float(v[u].z);
                m *= 0.125f;
#pragma unroll
                for (int u = 0; u < 4; u++) {
                  const float d = __uint_as_float(v[u].x) - m, f = __uint_as_float(v[u].z) - m;
                  var += fmaf(128.0f, fmaf(d, d, f * f), __uint_as_float(v[u].y) + __uint_as_float(v[u].w));
                }
                const float rs = rsqrtf(fmaf(var, 1.0f / 1024.0f, 1e-5f)), mr = -m * rs;
#pragma unroll
                for (int r = 0; r < 4; r++) { s[r] = __shfl_sync(0xffffffffu, rs, r, 4); q[r] = __shfl_sync(0xffffffffu, mr, r, 4); }
                STAMP_T(T > 1 ? 28 : 27);
                if (T == 1 && pass) bar_sync(5, 256);
#pragma unroll
                for (int g = 0; g < 4; g++) {
                  const uint4 sh = lds128(vg + 256 + (lane & 3) * 64 + g * 16), sc = lds128(vg + 512 + (lane & 3) * 64 + g * 16);
#pragma unroll
                  for (int u = 0; u < 4; u++) {
                    const float* a = &acc[u >> 1][16 * g + 8 * (u & 1)];
                    uint32_t o[4];
#pragma unroll
                    for (int i = 0; i < 4; i++) {
                      const int r = (u & 2) + (i & 1), c = 2 * (u & 1) + (i >> 1);
                      o[i] = fma2(pack2(fmaf(a[2 * i], s[r], q[r]), fmaf(a[2 * i + 1], s[r], q[r])), c == 0 ? sc.x : c == 1 ? sc.y : c == 2 ? sc.z : sc.w,
                                  c == 0 ? sh.x : c == 1 ? sh.y : c == 2 ? sh.z : sh.w);
                    }
                    stsm4_if(stbase + (u >> 1) * 8192 + (g >> 1) * 16384 + (x0 ^ ((2 * (g & 1) + (u & 1)) << 5)), o[0], o[1], o[2], o[3], pass);
                  }
                }
              } else {
#pragma unroll
                for (int i = 0; i < 16; i++)
                  stsm4(stbase + (i >> 3) * 8192 + ((i >> 2) & 1) * 16384 + (x0 ^ ((i & 3) << 5)), xr[i >> 3][(i & 7) * 4], xr[i >> 3][(i & 7) * 4 + 1],
                        xr[i >> 3][(i & 7) * 4 + 2], xr[i >> 3][(i & 7) * 4 + 3]);
              }
            }
            staged_arrive(sb, T - 1);
            STAMP_T(52 + T);
          } else if (T > 4) {
            epilogue_f1<128>(acc, stbase, x0);
            staged_arrive(sb, T - 1);
          } else if (T < 4) {
            const uint32_t a0 = sb + OFF_E1 + srow * 16 + (lane >> 4) * 2048;
#pragma unroll
            for (int j2 = 0; j2 < 4; j2++)
#pragma unroll
              for (int mb = 0; mb < 2; mb++) {
                const float* a = &acc[mb][32 + 8 * j2];
                stsm4(a0 + mb * 1024 + j2 * 4096 + (j2 >> 1) * 2048, pack2(a[0], a[1]), pack2(a[2], a[3]), pack2(a[4], a[5]), pack2(a[6], a[7]));
              }
            sts128(sb + OFF_E1 + 8192 + t * 16, make_uint4(0x3f803f80u, 0x3f803f80u, 0x3f803f80u, 0x3f803f80u));
#pragma unroll
            for (int i = 0; i < 32; i++) af[i] = pack2(acc[(i >> 3) & 1][(i & 16) + 2 * (i & 7)], acc[(i >> 3) & 1][(i & 16) + 2 * (i & 7) + 1]);
            mbar_wait(bars + B_INIT * 8, 0);
          } else {
#pragma unroll
            for (int j2 = 0; j2 < 8; j2++) {
              const float* a = &acc[1][8 * j2];
              stsm4(stbase + 8192 + (j2 >> 2) * 16384 + (x0 ^ ((j2 & 3) << 5)), pack2(a[0], a[1]), pack2(a[2], a[3]), pack2(a[4], a[5]), pack2(a[6], a[7]));
            }
            bar_arrive(5, 256);
#pragma unroll
            for (int i = 0; i < 32; i++) af[i] = pack2(acc[0][2 * i], acc[0][2 * i + 1]);
          }
          if ((T & 3) != 1) STAMP_T(52 + T);
        } else {
          bar_sync(5, 256);
#pragma unroll
          for (int j2 = 0; j2 < 8; j2++) ldsm4(stbase + 8192 + (j2 >> 2) * 16384 + (x0 ^ ((j2 & 3) << 5)), af[4 * j2], af[4 * j2 + 1], af[4 * j2 + 2], af[4 * j2 + 3]);
        }
        if (T < 2 || T > 4) continue;
        const bool isq = op == 4 || T == 4;
        float pq[2][2][16];
        float(&pp)[4][16] = reinterpret_cast<float(&)[4][16]>(pq);
        {
          const uint32_t blo = (d0 + (OFF_WPHI >> 4) + (isq ? 0 : ab * 256)) | 0x200000u, bs = isq ? 128 : 0;
#pragma unroll
          for (int u = 0; u < 4; u++) zero_regs(pp[u]);
          wg_fence();
#pragma unroll
          for (int u = 0; u < 4; u++) {
            const uint32_t b1 = blo + (u >> 1) * 128 + ((u + 1) >> 1) * bs;
            wgmma_rs_n32(pp[u], af[8 * u], af[8 * u + 1], af[8 * u + 2], af[8 * u + 3], mkdesc(b1, 8u), 0);
            wgmma_rs_n32(pp[u], af[8 * u + 4], af[8 * u + 5], af[8 * u + 6], af[8 * u + 7], mkdesc(b1 + 64, 8u), 1);
          }
          wg_commit();
          wg_wait<0>();
#pragma unroll
          for (int u = 0; u < 4; u++) fence_regs(pp[u]);
          if (!ab) STAMP_T(isq ? 33 : 17);
        }
        float kvs[2][20] = {};
#pragma unroll 1
        for (int it = 0; it < 2; it++) {
          float4 v[4] = {};
          float z = 0.f;
          if (isq) {
            mbar_wait(bars + (B_KVOK + it) * 8, 0);
#pragma unroll
            for (int u = 0; u < 4; u++) v[u] = ldcg4(g_kv + (4 * j + 2 * it) * 2048 + (wid - 4) * 512 + u * 128 + lane * 4);
            z = __ldcg(g_z + (4 * j + 2 * it) * 64 + t);
          }
          uint32_t f[2][16];
          feature_map(pq[0], f, !isq);
#pragma unroll
          for (int i = 0; i < 16; i++) { pp[0][i] = pp[2][i]; pp[1][i] = pp[3][i]; }
          float o[4][20];
#pragma unroll
          for (int u = 0; u < 4; u++) zero_regs(o[u]);
          if (isq) {
            const uint32_t dst = sb + OFF_E1 + it * 10240;
#pragma unroll
            for (int u = 0; u < 2; u++)
              stsm4(dst + (wid - 4) * 1280 + ((lane >> 3) & 1) * 640 + (lane >> 4) * 128 + u * 256 + (lane & 7) * 16, pack2(v[2 * u].x, v[2 * u].y),
                    pack2(v[2 * u].z, v[2 * u].w), pack2(v[2 * u + 1].x, v[2 * u + 1].y), pack2(v[2 * u + 1].z, v[2 * u + 1].w));
            const uint32_t z1 = pack2(z, 1.0f);
            sts128(dst + (t >> 3) * 640 + 512 + (t & 7) * 16, make_uint4(z1, z1, z1, z1));
            fence_async_smem();
            bar_sync(6, 256);
            if (!ab) STAMP_T(38 + it);
            const uint32_t kd = (d0 + (OFF_E1 >> 4) + it * 640) | (40u << 16);
            wg_fence();
#pragma unroll
            for (int k = 0; k < 8; k++) {
              const uint32_t* a = &f[k >> 2][4 * (k & 3)];
              wgmma_rs_n40(o[k >> 1], a[0], a[1], a[2], a[3], mkdesc(kd + k * 80, 8u), k & 1);
            }
            wg_commit();
            wg_wait<0>();
#pragma unroll
            for (int u = 0; u < 4; u++) fence_regs(o[u]);
            if (!ab) STAMP_T(62 + it);
#pragma unroll
            for (int u = 0; u < 2; u++) {
              const float(&a)[20] = o[2 * u];
              const float(&c)[20] = o[2 * u + 1];
              float ra[2], rc[2];
#pragma unroll
              for (int r = 0; r < 2; r++) {
                const float d = rcp(fmaf(a[16 + 2 * r], c[17 + 2 * r], a[17 + 2 * r] * fmaf(c[17 + 2 * r], 1e-6f, c[16 + 2 * r])));
                ra[r] = c[17 + 2 * r] * d; rc[r] = a[17 + 2 * r] * d;
              }
              uint32_t q[8];
#pragma unroll
              for (int i = 0; i < 8; i++) q[i] = pack2(fmaf(a[2 * i], ra[i & 1], c[2 * i] * rc[i & 1]), fmaf(a[2 * i + 1], ra[i & 1], c[2 * i + 1] * rc[i & 1]));
#pragma unroll
              for (int j2 = 0; j2 < 2; j2++) stsm4(stbase + it * 16384 + ab * 8192 + (x0 ^ ((u * 2 + j2) << 5)), q[4 * j2], q[4 * j2 + 1], q[4 * j2 + 2], q[4 * j2 + 3]);
            }
            staged_arrive(sb, it ? S_O : S_O0);
          } else {
            const uint32_t dst = sb + OFF_E0 + srow * 16 + (lane >> 4) * 2048 + it * 16384;
#pragma unroll
            for (int u = 0; u < 2; u++)
#pragma unroll
              for (int k = 0; k < 4; k++) stsm4(dst + u * 1024 + k * 4096, f[u][4 * k], f[u][4 * k + 1], f[u][4 * k + 2], f[u][4 * k + 3]);
            fence_async_smem();
            bar_sync(3 + ab, 128);
            if (!ab) STAMP_T(18 + it);
            float(&kv)[20] = o[0];
            const uint32_t ka = (d0 + (OFF_E0 >> 4) + it * 1024) | 0x80000u, kb = (d0 + (OFF_E1 >> 4) + it * 512) | 0x80000u;
            wg_fence();
#pragma unroll
            for (int ks = 0; ks < 8; ks++) wgmma_ss_n40_tt(kv, mkdesc(ka + ks * 16, 128u), mkdesc(kb + ks * 16, 128u), ks);
            wg_commit();
            wg_wait<0>();
            fence_regs(kv);
            if (!ab) STAMP_T(30 + it);
#pragma unroll
            for (int i = 0; i < 20; i++) { kvs[0][i] = kvs[1][i]; kvs[1][i] = kv[i]; }
          }
        }
        if (!isq) {
          const int fi = (4 * j + 2 * ab) * 64 + w * 16 + (lane >> 2);
          float* dk = g_kv + (4 * j + 2 * ab) * 2048 + w * 512 + lane * 4;
#pragma unroll
          for (int i = 0; i < 8; i++) red4(dk + (i >> 2) * 2048 + (i & 3) * 128, &kvs[i >> 2][4 * (i & 3) + (i & 4)]);
          red1(g_z + fi + (lane & 1) * 8 + (lane & 2) * 32, (lane & 2) ? ((lane & 1) ? kvs[1][2] : kvs[1][0]) : ((lane & 1) ? kvs[0][18] : kvs[0][16]));
          __syncwarp();
          mbar_arrive_e(bars + (B_STG + S_KV + ab) * 8);
        }
        STAMP_T(20 + 2 * isq + ab);
        zero_regs(xr[0]); zero_regs(xr[1]);
      } else {
        float acc[2][96];
        init_bias<192>(acc, sb + OFF_VEC + 2560);
        bar_sync(2, 256);
        mainloop<192>(acc, sb, 4, 0);
        STAMP_T(13);
        mbar_wait(bars + (B_EFREE + S_H2) * 8, 0);
        epilogue_f1<192>(acc, stbase, x0);
        staged_arrive(sb, S_F1);
        STAMP_T(58);
        zero_regs(xr[0]); zero_regs(xr[1]);
        T += 2;
      }
    }
    cluster_arrive(); cluster_wait();
  }
}

typedef CUresult (*EncodeFn)(CUtensorMap*, CUtensorMapDataType, cuuint32_t, void*, const cuuint64_t*, const cuuint64_t*, const cuuint32_t*,
                             const cuuint32_t*, CUtensorMapInterleave, CUtensorMapSwizzle, CUtensorMapL2promotion, CUtensorMapFloatOOBfill);

void make_map(EncodeFn fn, CUtensorMap* m, const void* ptr, int rows, int cols, int boxrows) {
  cuuint64_t dims[2] = {(cuuint64_t)cols, (cuuint64_t)rows};
  cuuint64_t str[1] = {(cuuint64_t)cols * 2};
  cuuint32_t box[2] = {64, (cuuint32_t)boxrows};
  cuuint32_t es[2] = {1, 1};
  fn(m, CU_TENSOR_MAP_DATA_TYPE_BFLOAT16, 2, const_cast<void*>(ptr), dims, str, box, es, CU_TENSOR_MAP_INTERLEAVE_NONE, CU_TENSOR_MAP_SWIZZLE_128B,
     CU_TENSOR_MAP_L2_PROMOTION_L2_128B, CU_TENSOR_MAP_FLOAT_OOB_FILL_NONE);
}
void make_map3(EncodeFn fn, CUtensorMap* m, const void* ptr, int rows, int cols, int part, int nb) {
  cuuint64_t dims[3] = {(cuuint64_t)part, (cuuint64_t)rows, (cuuint64_t)(cols / part)};
  cuuint64_t str[2] = {(cuuint64_t)cols * 2, (cuuint64_t)part * 2};
  cuuint32_t box[3] = {64, 64, (cuuint32_t)nb};
  cuuint32_t es[3] = {1, 1, 1};
  fn(m, CU_TENSOR_MAP_DATA_TYPE_BFLOAT16, 3, const_cast<void*>(ptr), dims, str, box, es, CU_TENSOR_MAP_INTERLEAVE_NONE, CU_TENSOR_MAP_SWIZZLE_128B,
     CU_TENSOR_MAP_L2_PROMOTION_L2_128B, CU_TENSOR_MAP_FLOAT_OOB_FILL_NONE);
}

}

extern "C" void kernel_launch(void* const* d_in, const int* in_sizes, int n_in, void* d_out, int out_size) {
  (void)in_sizes; (void)n_in; (void)out_size;
  static EncodeFn fn = nullptr;
  static void *p_o = nullptr, *p_h = nullptr, *p_h1 = nullptr;
  if (!fn) {
    void* f = nullptr; cudaDriverEntryPointQueryResult q;
    cudaGetDriverEntryPoint("cuTensorMapEncodeTiled", &f, cudaEnableDefault, &q);
    fn = (EncodeFn)f;
    cudaFuncSetAttribute(fused_block_kernel, cudaFuncAttributeMaxDynamicSharedMemorySize, SMEM_BYTES);
    cudaGetSymbolAddress(&p_o, g_o); cudaGetSymbolAddress(&p_h, g_h); cudaGetSymbolAddress(&p_h1, g_h1);
  }
  Params p;
  make_map(fn, &p.a_h, p_h, SEQ, DM, 64);
  make_map(fn, &p.a_o, p_o, SEQ, DM, 64);
  make_map(fn, &p.a_h1, p_h1, SEQ, FF, 64);
  make_map3(fn, &p.b_kv, d_in[1], DM, 3 * DM, 1024, 2);
  make_map3(fn, &p.b_q, d_in[1], DM, 3 * DM, 64, 2);
  make_map3(fn, &p.b_wo, d_in[3], DM, DM, 64, 2);
  make_map3(fn, &p.b_w1x, d_in[5], DM, FF, 64, 3);
  make_map3(fn, &p.b_w1, d_in[5], DM, FF, 64, 2);
  make_map3(fn, &p.b_w2, d_in[7], FF, DM, 64, 2);
  make_map(fn, &p.t_x, d_in[0], SEQ, DM, 128);
  make_map(fn, &p.t_h, p_h, SEQ, DM, 128);
  make_map(fn, &p.t_o, p_o, SEQ, DM, 128);
  make_map(fn, &p.t_h1, p_h1, SEQ, FF, 128);
  make_map(fn, &p.t_out, d_out, SEQ, DM, 128);
  p.wphi = (const bf16*)d_in[2]; p.b1 = (const bf16*)d_in[6]; p.b2 = (const bf16*)d_in[8];
  p.c = (const bf16*)d_in[9]; p.wmod = (const bf16*)d_in[10];
  fused_block_kernel<<<128, 384, SMEM_BYTES, cudaStreamPerThread>>>(p);
}
```
